```python
import torch

def _softmax(x, axis=-1):
    return torch.softmax(x, dim=axis)
def _gelu(x):
    return torch.nn.functional.gelu(x, approximate="tanh")
def _silu(x):
    return torch.nn.functional.silu(x)
def _sigmoid(x):
    return torch.sigmoid(x)
def _layernorm(x, axis=-1, eps=1e-5):
    m = x.mean(dim=axis, keepdim=True)
    v = x.var(dim=axis, keepdim=True, unbiased=False)
    return (x - m) / torch.sqrt(v + eps)
def _scatter_add(tgt, idx, src, axis=0):
    return tgt.clone().index_add_(axis, idx, src)
def _segment_sum(src, seg, n):
    out = torch.zeros((n,) + src.shape[1:], dtype=src.dtype)
    return out.index_add_(0, seg, src)
def _pad(x, pw):
    flat = tuple(v for pair in reversed(pw) for v in pair)
    return torch.nn.functional.pad(x, flat)

kernel_name = 'parallel_sum__sliding_local_dilated__dense_activation_relu__prompt'

def setup_inputs():

    _w = (lambda a: (lambda t: t.to(torch.bfloat16) if t.is_floating_point() else t)(torch.as_tensor(a)))
    def _A_setup():
        B, S, D = 1, 2048, 512
        return {
            "x": _w((lambda *s: torch.randn(*s, dtype=torch.bfloat16) * 0.05)(B, S, D)),
            "wqkv": _w((lambda *s: torch.randn(*s, dtype=torch.bfloat16) * 0.05)(D, 3 * D)),
            "wo": _w((lambda *s: torch.randn(*s, dtype=torch.bfloat16) * 0.05)(D, D)),
        }
    _A_in = _A_setup()

    def _B_setup():
        B, S, D, Dff = 1, 2048, 512, 1376
        return {
            "x": _w((lambda *s: torch.randn(*s, dtype=torch.bfloat16) * 0.05)(B, S, D)),
            "w1": _w((lambda *s: torch.randn(*s, dtype=torch.bfloat16) * 0.05)(D, Dff)),
            "w2": _w((lambda *s: torch.randn(*s, dtype=torch.bfloat16) * 0.05)(Dff, D)),
        }
    _B_in = _B_setup()

    return {
        "A_x": _A_in["x"],
        "A_wqkv": _A_in["wqkv"],
        "A_wo": _A_in["wo"],
        "B_x": _B_in["x"],
        "B_w1": _B_in["w1"],
        "B_w2": _B_in["w2"],
    }

def reference(A_x, A_wqkv, A_wo, B_x, B_w1, B_w2):
    def _A_ref(x, wqkv, wo):
        B, S, D = x.shape
        H = 32; Dh = D // H
        W, dil = 8, 2
        qkv = (lambda x, *d: x.permute(*d))((x @ wqkv).reshape(B, S, 3, H, Dh), 2, 0, 3, 1, 4)
        q, k, v = qkv[0], qkv[1], qkv[2]
        scale = Dh ** -0.5
        pos = torch.arange(S)
        off = torch.arange(W) * dil
        idx = pos[:, None] - off[None, :]
        mask = idx >= 0
        idx_c = torch.where(mask, idx, 0).reshape(-1)
        kg = k[:, :, idx_c, :].reshape(B, H, S, W, Dh)
        vg = v[:, :, idx_c, :].reshape(B, H, S, W, Dh)
        logits = torch.einsum("bhsd,bhswd->bhsw", q, kg) * scale
        logits = torch.where(mask[None, None, :, :], logits, -1e9)
        attn = _softmax(logits, axis=-1)
        o = torch.einsum("bhsw,bhswd->bhsd", attn, vg)
        return (lambda x, *d: x.permute(*d))(o, 0, 2, 1, 3).reshape(B, S, D) @ wo

    def _B_ref(x, w1, w2):
        h = torch.einsum("bsd,df->bsf", x, w1)
        zero = torch.zeros_like(h)
        h = torch.maximum(h, zero)
        return torch.einsum("bsf,fd->bsd", h, w2)

    x = A_x
    xn = _layernorm(x, axis=-1)
    return x + _A_ref(xn, A_wqkv, A_wo) + _B_ref(xn, B_w1, B_w2)
```

```cpp
#include <cuda_runtime.h>
#include <cuda_bf16.h>
#include <cuda.h>
#include <stdint.h>

namespace fused {

constexpr int NTOK = 2048, DM = 512, DFF = 1376;
constexpr int NTHREADS = 384;
constexpr int NCTA = 128;

constexpr uint32_t XN_OFF   = 0;
constexpr uint32_t RING_OFF = 131072;
constexpr uint32_t S_SLOT   = 24576;
constexpr uint32_t U_SLOT   = 30720;
constexpr uint32_t BAR_OFF  = RING_OFF + 4 * S_SLOT;
constexpr uint32_t B_XFULL  = BAR_OFF;
constexpr uint32_t B_FULLA  = BAR_OFF + 64;
constexpr uint32_t B_EMPTYA = BAR_OFF + 96;
constexpr uint32_t B_FULLB  = BAR_OFF + 128;
constexpr uint32_t B_EMPTYB = BAR_OFF + 152;
constexpr uint32_t B_FREE   = BAR_OFF + 176;
constexpr uint32_t B_RDYH   = BAR_OFF + 192;
constexpr uint32_t B_RDYO   = BAR_OFF + 208;
constexpr uint32_t B_A2FULL = BAR_OFF + 224;
constexpr uint32_t B_PEERDN = BAR_OFF + 240;
constexpr uint32_t B_CSQ    = BAR_OFF + 248;
constexpr uint32_t B_CSF    = BAR_OFF + 256;
constexpr uint32_t B_XDEAD  = BAR_OFF + 264;
constexpr uint32_t B_HALO   = BAR_OFF + 280;
constexpr uint32_t EPO_OFF  = BAR_OFF + 296;
constexpr uint32_t B_SND    = BAR_OFF + 304;
constexpr uint32_t CSQ_OFF  = BAR_OFF + 352;
constexpr uint32_t CS_STR   = 208;
constexpr uint32_t CSF_OFF  = CSQ_OFF + 4 * CS_STR;
constexpr uint32_t SMEM_END = CSF_OFF + 4 * CS_STR;
constexpr uint32_t SMEM_BYTES = SMEM_END + 1024;
static_assert(SMEM_BYTES <= 232448, "shared memory budget");

struct Scratch {
  ulonglong2 part[NCTA * 3 * 2 * 4 * 128];
  ulonglong2 halo[NCTA * 2 * 8 * 32];
  uint4      cs[8 * 2 * 16 * 48];
  uint2      stats[NTOK];
  unsigned   epoch[NCTA];
};
__device__ Scratch g_scratch;

#define TS(slot) do { } while (0)
#define TSH(slot) do { } while (0)

__device__ __forceinline__ uint32_t smem_u32(const void* p) { return (uint32_t)__cvta_generic_to_shared(p); }
__device__ __forceinline__ void mbar_init(uint32_t bar, uint32_t cnt) {
  asm volatile("mbarrier.init.shared::cta.b64 [%0], %1;" ::"r"(bar), "r"(cnt) : "memory");
}
__device__ __forceinline__ void mbar_expect_tx(uint32_t bar, uint32_t bytes) {
  asm volatile("mbarrier.arrive.expect_tx.shared::cta.b64 _, [%0], %1;" ::"r"(bar), "r"(bytes) : "memory");
}
__device__ __forceinline__ void mbar_arrive(uint32_t bar) {
  asm volatile("mbarrier.arrive.shared::cta.b64 _, [%0];" ::"r"(bar) : "memory");
}
__device__ __forceinline__ uint32_t mapa(uint32_t addr, uint32_t rank) {
  uint32_t r;
  asm("mapa.shared::cluster.u32 %0, %1, %2;" : "=r"(r) : "r"(addr), "r"(rank));
  return r;
}
__device__ __forceinline__ void mbar_arrive_remote(uint32_t cluster_addr) {
  asm volatile("mbarrier.arrive.relaxed.cluster.shared::cluster.b64 _, [%0];" ::"r"(cluster_addr) : "memory");
}
constexpr uint32_t SPIN_LIMIT = 1u << 18;
__device__ __forceinline__ void mbar_wait(uint32_t bar, uint32_t parity) {
  uint32_t ok, n = 0;
  do {
    asm volatile("{\n.reg .pred p;\nmbarrier.try_wait.parity.shared::cta.b64 p, [%1], %2;\nselp.u32 %0, 1, 0, p;\n}"
                 : "=r"(ok) : "r"(bar), "r"(parity) : "memory");
  } while (!ok && ++n < SPIN_LIMIT);
}
__device__ __forceinline__ void mbar_wait_cluster(uint32_t bar, uint32_t parity) {
  uint32_t ok, n = 0;
  do {
    asm volatile("{\n.reg .pred p;\nmbarrier.try_wait.parity.acquire.cluster.shared::cta.b64 p, [%1], %2;\nselp.u32 %0, 1, 0, p;\n}"
                 : "=r"(ok) : "r"(bar), "r"(parity) : "memory");
  } while (!ok && ++n < SPIN_LIMIT);
}
__device__ __forceinline__ bool elect_one() {
  uint32_t p;
  asm volatile("{\n.reg .pred P;\nelect.sync _|P, 0xffffffff;\nselp.u32 %0, 1, 0, P;\n}" : "=r"(p));
  return p != 0;
}
__device__ __forceinline__ void tma2d(uint32_t dst, const CUtensorMap* m, uint32_t bar, int c0, int c1) {
  asm volatile("cp.async.bulk.tensor.2d.shared::cluster.global.mbarrier::complete_tx::bytes [%0], [%1, {%3, %4}], [%2];"
               ::"r"(dst), "l"(m), "r"(bar), "r"(c0), "r"(c1) : "memory");
}
__device__ __forceinline__ void tma3d(uint32_t dst, const CUtensorMap* m, uint32_t bar, int c0, int c1, int c2) {
  asm volatile("cp.async.bulk.tensor.3d.shared::cluster.global.mbarrier::complete_tx::bytes [%0], [%1, {%3, %4, %5}], [%2];"
               ::"r"(dst), "l"(m), "r"(bar), "r"(c0), "r"(c1), "r"(c2) : "memory");
}
__device__ __forceinline__ void tma3d_mc(uint32_t dst, const CUtensorMap* m, uint32_t bar, int c0, int c1, int c2, uint16_t mask) {
  asm volatile("cp.async.bulk.tensor.3d.shared::cluster.global.mbarrier::complete_tx::bytes.multicast::cluster [%0], [%1, {%3, %4, %5}], [%2], %6;"
               ::"r"(dst), "l"(m), "r"(bar), "r"(c0), "r"(c1), "r"(c2), "h"(mask) : "memory");
}
__device__ __forceinline__ void tma3d_store(const CUtensorMap* m, uint32_t src, int c0, int c1, int c2) {
  asm volatile("cp.async.bulk.tensor.3d.global.shared::cta.bulk_group [%0, {%2, %3, %4}], [%1];"
               ::"l"(m), "r"(src), "r"(c0), "r"(c1), "r"(c2) : "memory");
}
__device__ __forceinline__ void tma2d_prefetch(const CUtensorMap* m, int c0, int c1) {
  asm volatile("cp.async.bulk.prefetch.tensor.2d.L2.global [%0, {%1, %2}];" ::"l"(m), "r"(c0), "r"(c1) : "memory");
}
__device__ __forceinline__ void prefetch_tmap(const CUtensorMap* m) {
  asm volatile("prefetch.tensormap [%0];" ::"l"(m) : "memory");
}
__device__ __forceinline__ void bulk_s2s(uint32_t dst_cluster, uint32_t src, uint32_t bytes, uint32_t bar_cluster) {
  asm volatile("cp.async.bulk.shared::cluster.shared::cta.mbarrier::complete_tx::bytes [%0], [%1], %2, [%3];"
               ::"r"(dst_cluster), "r"(src), "r"(bytes), "r"(bar_cluster) : "memory");
}
__device__ __forceinline__ void st_async_v4(uint32_t dst_cluster, const uint4& v, uint32_t bar_cluster) {
  asm volatile("st.async.weak.shared::cluster.mbarrier::complete_tx::bytes.v4.b32 [%0], {%1,%2,%3,%4}, [%5];"
               ::"r"(dst_cluster), "r"(v.x), "r"(v.y), "r"(v.z), "r"(v.w), "r"(bar_cluster) : "memory");
}
__device__ __forceinline__ uint4 lds128(uint32_t addr) {
  uint4 v;
  asm volatile("ld.shared.v4.b32 {%0,%1,%2,%3}, [%4];" : "=r"(v.x), "=r"(v.y), "=r"(v.z), "=r"(v.w) : "r"(addr));
  return v;
}
__device__ __forceinline__ uint4 lds128_nv(uint32_t addr) {
  uint4 v;
  asm("ld.shared.v4.b32 {%0,%1,%2,%3}, [%4];" : "=r"(v.x), "=r"(v.y), "=r"(v.z), "=r"(v.w) : "r"(addr));
  return v;
}
__device__ __forceinline__ float4 lds128f(uint32_t addr) {
  float4 v;
  asm("ld.shared.v4.f32 {%0,%1,%2,%3}, [%4];" : "=f"(v.x), "=f"(v.y), "=f"(v.z), "=f"(v.w) : "r"(addr));
  return v;
}
__device__ __forceinline__ float4 lds128f_v(uint32_t addr) {
  float4 v;
  asm volatile("ld.shared.v4.f32 {%0,%1,%2,%3}, [%4];" : "=f"(v.x), "=f"(v.y), "=f"(v.z), "=f"(v.w) : "r"(addr));
  return v;
}
__device__ __forceinline__ float2 lds64f(uint32_t addr) {
  float2 v;
  asm("ld.shared.v2.f32 {%0,%1}, [%2];" : "=f"(v.x), "=f"(v.y) : "r"(addr));
  return v;
}
__device__ __forceinline__ uint4 ldg_nc(const uint4* p) {
  uint4 v;
  asm volatile("ld.global.nc.v4.b32 {%0,%1,%2,%3}, [%4];" : "=r"(v.x), "=r"(v.y), "=r"(v.z), "=r"(v.w) : "l"(p));
  return v;
}
__device__ __forceinline__ void fence_async_smem() { asm volatile("fence.proxy.async.shared::cta;" ::: "memory"); }
__device__ __forceinline__ void wg_bar(int id) { asm volatile("bar.sync %0, 128;" ::"r"(id) : "memory"); }
__device__ __forceinline__ void wg_fence() { asm volatile("wgmma.fence.sync.aligned;" ::: "memory"); }
__device__ __forceinline__ void wg_commit() { asm volatile("wgmma.commit_group.sync.aligned;" ::: "memory"); }
template <int N> __device__ __forceinline__ void wg_wait() { asm volatile("wgmma.wait_group.sync.aligned %0;" ::"n"(N) : "memory"); }
template <int N> __device__ __forceinline__ void reg_fence(float (&d)[N]) {
#pragma unroll
  for (int i = 0; i < N; i++) asm volatile("" : "+f"(d[i])::"memory");
}
__device__ __forceinline__ void ldsm4(uint32_t (&r)[4], uint32_t addr) {
  asm volatile("ldmatrix.sync.aligned.m8n8.x4.shared.b16 {%0,%1,%2,%3}, [%4];"
               : "=r"(r[0]), "=r"(r[1]), "=r"(r[2]), "=r"(r[3]) : "r"(addr) : "memory");
}
__device__ __forceinline__ void stsm4(uint32_t addr, uint32_t r0, uint32_t r1, uint32_t r2, uint32_t r3) {
  asm volatile("stmatrix.sync.aligned.m8n8.x4.shared.b16 [%0], {%1,%2,%3,%4};"
               ::"r"(addr), "r"(r0), "r"(r1), "r"(r2), "r"(r3) : "memory");
}
__device__ __forceinline__ void mma16816(float (&c)[4], uint32_t a0, uint32_t a1, uint32_t a2, uint32_t a3, uint32_t b0, uint32_t b1) {
  asm("mma.sync.aligned.m16n8k16.row.col.f32.bf16.bf16.f32 {%0,%1,%2,%3}, {%4,%5,%6,%7}, {%8,%9}, {%0,%1,%2,%3};"
               : "+f"(c[0]), "+f"(c[1]), "+f"(c[2]), "+f"(c[3]) : "r"(a0), "r"(a1), "r"(a2), "r"(a3), "r"(b0), "r"(b1));
}
__device__ __forceinline__ void mma1688(float (&c)[4], uint32_t a0, uint32_t a1, uint32_t b0) {
  asm("mma.sync.aligned.m16n8k8.row.col.f32.bf16.bf16.f32 {%0,%1,%2,%3}, {%4,%5}, {%6}, {%0,%1,%2,%3};"
               : "+f"(c[0]), "+f"(c[1]), "+f"(c[2]), "+f"(c[3]) : "r"(a0), "r"(a1), "r"(b0));
}
__device__ __forceinline__ uint32_t movm(uint32_t a) {
  uint32_t d;
  asm volatile("movmatrix.sync.aligned.m8n8.trans.b16 %0, %1;" : "=r"(d) : "r"(a));
  return d;
}
__device__ __forceinline__ uint32_t pack2(float lo, float hi) {
  uint32_t d;
  asm("cvt.rn.bf16x2.f32 %0, %1, %2;" : "=r"(d) : "f"(hi), "f"(lo));
  return d;
}
__device__ __forceinline__ uint32_t pack2_relu(float lo, float hi) {
  uint32_t d;
  asm("cvt.rn.relu.bf16x2.f32 %0, %1, %2;" : "=r"(d) : "f"(hi), "f"(lo));
  return d;
}
__device__ __forceinline__ uint32_t hfma2_bf16(uint32_t a, uint32_t b, uint32_t c) {
  uint32_t d;
  asm("fma.rn.bf16x2 %0, %1, %2, %3;" : "=r"(d) : "r"(a), "r"(b), "r"(c));
  return d;
}
__device__ __forceinline__ float bf_lo(uint32_t v) { return __uint_as_float(v << 16); }
__device__ __forceinline__ float bf_hi(uint32_t v) { return __uint_as_float(v & 0xffff0000u); }
__device__ __forceinline__ float ex2(float x) { float y; asm("ex2.approx.ftz.f32 %0, %1;" : "=f"(y) : "f"(x)); return y; }
__device__ __forceinline__ void st_relaxed_v2(ulonglong2* p, uint64_t a, uint64_t b) {
  asm volatile("st.relaxed.gpu.global.v2.b64 [%0], {%1, %2};" ::"l"(p), "l"(a), "l"(b) : "memory");
}
__device__ __forceinline__ void ld_relaxed_v2(const ulonglong2* p, uint64_t& a, uint64_t& b) {
  asm volatile("ld.relaxed.gpu.global.v2.b64 {%0, %1}, [%2];" : "=l"(a), "=l"(b) : "l"(p) : "memory");
}
__device__ __forceinline__ uint64_t mk64(uint32_t lo, uint32_t hi) { return ((uint64_t)hi << 32) | lo; }

__device__ __forceinline__ uint32_t fresh_tid() { uint32_t t; asm volatile("mov.u32 %0, %%tid.x;" : "=r"(t)); return t; }
__device__ __forceinline__ uint32_t fresh_cta() { uint32_t t; asm volatile("mov.u32 %0, %%ctaid.x;" : "=r"(t)); return t; }
__device__ __forceinline__ uint32_t fresh_u32(uint32_t v) { asm volatile("" : "+r"(v)); return v; }

__device__ __forceinline__ uint64_t desc_a(uint32_t addr) {
  return (uint64_t)((addr >> 4) & 0x3FFF) | (1ull << 16) | (64ull << 32) | (1ull << 62);
}
__device__ __forceinline__ uint64_t desc_b(uint32_t addr) {
  return (uint64_t)((addr >> 4) & 0x3FFF) | (512ull << 16) | (64ull << 32) | (1ull << 62);
}

__device__ __forceinline__ void wgmma_n192(float (&d)[96], uint64_t da, uint64_t db, int scale_d) {
  asm volatile("{\n.reg .pred p;\nsetp.ne.b32 p, %98, 0;\n"
    "wgmma.mma_async.sync.aligned.m64n192k16.f32.bf16.bf16 "
    "{%0, %1, %2, %3, %4, %5, %6, %7, %8, %9, %10, %11, %12, %13, %14, %15, "
    "%16, %17, %18, %19, %20, %21, %22, %23, %24, %25, %26, %27, %28, %29, %30, %31, "
    "%32, %33, %34, %35, %36, %37, %38, %39, %40, %41, %42, %43, %44, %45, %46, %47, "
    "%48, %49, %50, %51, %52, %53, %54, %55, %56, %57, %58, %59, %60, %61, %62, %63, "
    "%64, %65, %66, %67, %68, %69, %70, %71, %72, %73, %74, %75, %76, %77, %78, %79, "
    "%80, %81, %82, %83, %84, %85, %86, %87, %88, %89, %90, %91, %92, %93, %94, %95}, "
    "%96, %97, p, 1, 1, 0, 1;\n}\n"
    : "+f"(d[0]), "+f"(d[1]), "+f"(d[2]), "+f"(d[3]), "+f"(d[4]), "+f"(d[5]), "+f"(d[6]), "+f"(d[7]),
      "+f"(d[8]), "+f"(d[9]), "+f"(d[10]), "+f"(d[11]), "+f"(d[12]), "+f"(d[13]), "+f"(d[14]), "+f"(d[15]),
      "+f"(d[16]), "+f"(d[17]), "+f"(d[18]), "+f"(d[19]), "+f"(d[20]), "+f"(d[21]), "+f"(d[22]), "+f"(d[23]),
      "+f"(d[24]), "+f"(d[25]), "+f"(d[26]), "+f"(d[27]), "+f"(d[28]), "+f"(d[29]), "+f"(d[30]), "+f"(d[31]),
      "+f"(d[32]), "+f"(d[33]), "+f"(d[34]), "+f"(d[35]), "+f"(d[36]), "+f"(d[37]), "+f"(d[38]), "+f"(d[39]),
      "+f"(d[40]), "+f"(d[41]), "+f"(d[42]), "+f"(d[43]), "+f"(d[44]), "+f"(d[45]), "+f"(d[46]), "+f"(d[47]),
      "+f"(d[48]), "+f"(d[49]), "+f"(d[50]), "+f"(d[51]), "+f"(d[52]), "+f"(d[53]), "+f"(d[54]), "+f"(d[55]),
      "+f"(d[56]), "+f"(d[57]), "+f"(d[58]), "+f"(d[59]), "+f"(d[60]), "+f"(d[61]), "+f"(d[62]), "+f"(d[63]),
      "+f"(d[64]), "+f"(d[65]), "+f"(d[66]), "+f"(d[67]), "+f"(d[68]), "+f"(d[69]), "+f"(d[70]), "+f"(d[71]),
      "+f"(d[72]), "+f"(d[73]), "+f"(d[74]), "+f"(d[75]), "+f"(d[76]), "+f"(d[77]), "+f"(d[78]), "+f"(d[79]),
      "+f"(d[80]), "+f"(d[81]), "+f"(d[82]), "+f"(d[83]), "+f"(d[84]), "+f"(d[85]), "+f"(d[86]), "+f"(d[87]),
      "+f"(d[88]), "+f"(d[89]), "+f"(d[90]), "+f"(d[91]), "+f"(d[92]), "+f"(d[93]), "+f"(d[94]), "+f"(d[95])
    : "l"(da), "l"(db), "r"(scale_d));
}
__device__ __forceinline__ void wgmma_n176(float (&d)[88], uint64_t da, uint64_t db, int scale_d) {
  asm volatile("{\n.reg .pred p;\nsetp.ne.b32 p, %90, 0;\n"
    "wgmma.mma_async.sync.aligned.m64n176k16.f32.bf16.bf16 "
    "{%0, %1, %2, %3, %4, %5, %6, %7, %8, %9, %10, %11, %12, %13, %14, %15, "
    "%16, %17, %18, %19, %20, %21, %22, %23, %24, %25, %26, %27, %28, %29, %30, %31, "
    "%32, %33, %34, %35, %36, %37, %38, %39, %40, %41, %42, %43, %44, %45, %46, %47, "
    "%48, %49, %50, %51, %52, %53, %54, %55, %56, %57, %58, %59, %60, %61, %62, %63, "
    "%64, %65, %66, %67, %68, %69, %70, %71, %72, %73, %74, %75, %76, %77, %78, %79, "
    "%80, %81, %82, %83, %84, %85, %86, %87}, "
    "%88, %89, p, 1, 1, 0, 1;\n}\n"
    : "+f"(d[0]), "+f"(d[1]), "+f"(d[2]), "+f"(d[3]), "+f"(d[4]), "+f"(d[5]), "+f"(d[6]), "+f"(d[7]),
      "+f"(d[8]), "+f"(d[9]), "+f"(d[10]), "+f"(d[11]), "+f"(d[12]), "+f"(d[13]), "+f"(d[14]), "+f"(d[15]),
      "+f"(d[16]), "+f"(d[17]), "+f"(d[18]), "+f"(d[19]), "+f"(d[20]), "+f"(d[21]), "+f"(d[22]), "+f"(d[23]),
      "+f"(d[24]), "+f"(d[25]), "+f"(d[26]), "+f"(d[27]), "+f"(d[28]), "+f"(d[29]), "+f"(d[30]), "+f"(d[31]),
      "+f"(d[32]), "+f"(d[33]), "+f"(d[34]), "+f"(d[35]), "+f"(d[36]), "+f"(d[37]), "+f"(d[38]), "+f"(d[39]),
      "+f"(d[40]), "+f"(d[41]), "+f"(d[42]), "+f"(d[43]), "+f"(d[44]), "+f"(d[45]), "+f"(d[46]), "+f"(d[47]),
      "+f"(d[48]), "+f"(d[49]), "+f"(d[50]), "+f"(d[51]), "+f"(d[52]), "+f"(d[53]), "+f"(d[54]), "+f"(d[55]),
      "+f"(d[56]), "+f"(d[57]), "+f"(d[58]), "+f"(d[59]), "+f"(d[60]), "+f"(d[61]), "+f"(d[62]), "+f"(d[63]),
      "+f"(d[64]), "+f"(d[65]), "+f"(d[66]), "+f"(d[67]), "+f"(d[68]), "+f"(d[69]), "+f"(d[70]), "+f"(d[71]),
      "+f"(d[72]), "+f"(d[73]), "+f"(d[74]), "+f"(d[75]), "+f"(d[76]), "+f"(d[77]), "+f"(d[78]), "+f"(d[79]),
      "+f"(d[80]), "+f"(d[81]), "+f"(d[82]), "+f"(d[83]), "+f"(d[84]), "+f"(d[85]), "+f"(d[86]), "+f"(d[87])
    : "l"(da), "l"(db), "r"(scale_d));
}
__device__ __forceinline__ void wgmma_n176_init(float (&d)[88], uint64_t da, uint64_t db) {
  asm volatile("{\n.reg .pred p;\nsetp.ne.b32 p, 0, 0;\n"
    "wgmma.mma_async.sync.aligned.m64n176k16.f32.bf16.bf16 "
    "{%0, %1, %2, %3, %4, %5, %6, %7, %8, %9, %10, %11, %12, %13, %14, %15, "
    "%16, %17, %18, %19, %20, %21, %22, %23, %24, %25, %26, %27, %28, %29, %30, %31, "
    "%32, %33, %34, %35, %36, %37, %38, %39, %40, %41, %42, %43, %44, %45, %46, %47, "
    "%48, %49, %50, %51, %52, %53, %54, %55, %56, %57, %58, %59, %60, %61, %62, %63, "
    "%64, %65, %66, %67, %68, %69, %70, %71, %72, %73, %74, %75, %76, %77, %78, %79, "
    "%80, %81, %82, %83, %84, %85, %86, %87}, "
    "%88, %89, p, 1, 1, 0, 1;\n}\n"
    : "=f"(d[0]), "=f"(d[1]), "=f"(d[2]), "=f"(d[3]), "=f"(d[4]), "=f"(d[5]), "=f"(d[6]), "=f"(d[7]),
      "=f"(d[8]), "=f"(d[9]), "=f"(d[10]), "=f"(d[11]), "=f"(d[12]), "=f"(d[13]), "=f"(d[14]), "=f"(d[15]),
      "=f"(d[16]), "=f"(d[17]), "=f"(d[18]), "=f"(d[19]), "=f"(d[20]), "=f"(d[21]), "=f"(d[22]), "=f"(d[23]),
      "=f"(d[24]), "=f"(d[25]), "=f"(d[26]), "=f"(d[27]), "=f"(d[28]), "=f"(d[29]), "=f"(d[30]), "=f"(d[31]),
      "=f"(d[32]), "=f"(d[33]), "=f"(d[34]), "=f"(d[35]), "=f"(d[36]), "=f"(d[37]), "=f"(d[38]), "=f"(d[39]),
      "=f"(d[40]), "=f"(d[41]), "=f"(d[42]), "=f"(d[43]), "=f"(d[44]), "=f"(d[45]), "=f"(d[46]), "=f"(d[47]),
      "=f"(d[48]), "=f"(d[49]), "=f"(d[50]), "=f"(d[51]), "=f"(d[52]), "=f"(d[53]), "=f"(d[54]), "=f"(d[55]),
      "=f"(d[56]), "=f"(d[57]), "=f"(d[58]), "=f"(d[59]), "=f"(d[60]), "=f"(d[61]), "=f"(d[62]), "=f"(d[63]),
      "=f"(d[64]), "=f"(d[65]), "=f"(d[66]), "=f"(d[67]), "=f"(d[68]), "=f"(d[69]), "=f"(d[70]), "=f"(d[71]),
      "=f"(d[72]), "=f"(d[73]), "=f"(d[74]), "=f"(d[75]), "=f"(d[76]), "=f"(d[77]), "=f"(d[78]), "=f"(d[79]),
      "=f"(d[80]), "=f"(d[81]), "=f"(d[82]), "=f"(d[83]), "=f"(d[84]), "=f"(d[85]), "=f"(d[86]), "=f"(d[87])
    : "l"(da), "l"(db));
}
__device__ __forceinline__ void wgmma_n64_rs_init(float (&d)[32], const uint32_t (&a)[4], uint64_t db) {
  asm volatile("{\n.reg .pred p;\nsetp.ne.b32 p, 0, 0;\n"
    "wgmma.mma_async.sync.aligned.m64n64k16.f32.bf16.bf16 "
    "{%0, %1, %2, %3, %4, %5, %6, %7, %8, %9, %10, %11, %12, %13, %14, %15, "
    "%16, %17, %18, %19, %20, %21, %22, %23, %24, %25, %26, %27, %28, %29, %30, %31}, "
    "{%32, %33, %34, %35}, %36, p, 1, 1, 1;\n}\n"
    : "=f"(d[0]), "=f"(d[1]), "=f"(d[2]), "=f"(d[3]), "=f"(d[4]), "=f"(d[5]), "=f"(d[6]), "=f"(d[7]),
      "=f"(d[8]), "=f"(d[9]), "=f"(d[10]), "=f"(d[11]), "=f"(d[12]), "=f"(d[13]), "=f"(d[14]), "=f"(d[15]),
      "=f"(d[16]), "=f"(d[17]), "=f"(d[18]), "=f"(d[19]), "=f"(d[20]), "=f"(d[21]), "=f"(d[22]), "=f"(d[23]),
      "=f"(d[24]), "=f"(d[25]), "=f"(d[26]), "=f"(d[27]), "=f"(d[28]), "=f"(d[29]), "=f"(d[30]), "=f"(d[31])
    : "r"(a[0]), "r"(a[1]), "r"(a[2]), "r"(a[3]), "l"(db));
}
__device__ __forceinline__ void wgmma_n64_rs(float (&d)[32], const uint32_t (&a)[4], uint64_t db, int scale_d) {
  asm volatile("{\n.reg .pred p;\nsetp.ne.b32 p, %37, 0;\n"
    "wgmma.mma_async.sync.aligned.m64n64k16.f32.bf16.bf16 "
    "{%0, %1, %2, %3, %4, %5, %6, %7, %8, %9, %10, %11, %12, %13, %14, %15, "
    "%16, %17, %18, %19, %20, %21, %22, %23, %24, %25, %26, %27, %28, %29, %30, %31}, "
    "{%32, %33, %34, %35}, %36, p, 1, 1, 1;\n}\n"
    : "+f"(d[0]), "+f"(d[1]), "+f"(d[2]), "+f"(d[3]), "+f"(d[4]), "+f"(d[5]), "+f"(d[6]), "+f"(d[7]),
      "+f"(d[8]), "+f"(d[9]), "+f"(d[10]), "+f"(d[11]), "+f"(d[12]), "+f"(d[13]), "+f"(d[14]), "+f"(d[15]),
      "+f"(d[16]), "+f"(d[17]), "+f"(d[18]), "+f"(d[19]), "+f"(d[20]), "+f"(d[21]), "+f"(d[22]), "+f"(d[23]),
      "+f"(d[24]), "+f"(d[25]), "+f"(d[26]), "+f"(d[27]), "+f"(d[28]), "+f"(d[29]), "+f"(d[30]), "+f"(d[31])
    : "r"(a[0]), "r"(a[1]), "r"(a[2]), "r"(a[3]), "l"(db), "r"(scale_d));
}

__device__ __forceinline__ void attn4(const uint32_t (&q)[4][4], const uint32_t (&kk)[4][4], const uint32_t (&vt)[4][4],
                                      const uint32_t (&hv)[16], bool halo_valid, bool gt0, bool gt1, uint32_t (&o)[4][4]) {
  float l0[4], l1[4], h0[4], h1[4];
  const float NEG = -1e30f;
#pragma unroll
  for (int h = 0; h < 4; h++) {
    float s0[4] = {0.f, 0.f, 0.f, 0.f}, s1[4] = {0.f, 0.f, 0.f, 0.f}, s2[4] = {0.f, 0.f, 0.f, 0.f};
    mma16816(s0, q[h][0], q[h][1], q[h][2], q[h][3], hv[4 * h + 0], hv[4 * h + 1]);
    mma16816(s1, q[h][0], q[h][1], q[h][2], q[h][3], kk[h][0], kk[h][1]);
    mma16816(s2, q[h][0], q[h][1], q[h][2], q[h][3], kk[h][2], kk[h][3]);
    l0[h] = gt0 ? (halo_valid ? s0[0] : NEG) : s1[0];
    l1[h] = gt1 ? (halo_valid ? s0[1] : NEG) : s1[1];
    h0[h] = gt0 ? s1[2] : s2[2];
    h1[h] = gt1 ? s1[3] : s2[3];
  }
  float ml[4], mh[4];
#pragma unroll
  for (int h = 0; h < 4; h++) { ml[h] = fmaxf(l0[h], l1[h]); mh[h] = fmaxf(h0[h], h1[h]); }
#pragma unroll
  for (int h = 0; h < 4; h++) { ml[h] = fmaxf(ml[h], __shfl_xor_sync(0xffffffffu, ml[h], 1)); mh[h] = fmaxf(mh[h], __shfl_xor_sync(0xffffffffu, mh[h], 1)); }
#pragma unroll
  for (int h = 0; h < 4; h++) { ml[h] = fmaxf(ml[h], __shfl_xor_sync(0xffffffffu, ml[h], 2)); mh[h] = fmaxf(mh[h], __shfl_xor_sync(0xffffffffu, mh[h], 2)); }
  const float C = 0.25f * 1.4426950408889634f;
  float sl[4], sh[4];
#pragma unroll
  for (int h = 0; h < 4; h++) {
    l0[h] = ex2((l0[h] - ml[h]) * C); l1[h] = ex2((l1[h] - ml[h]) * C);
    h0[h] = ex2((h0[h] - mh[h]) * C); h1[h] = ex2((h1[h] - mh[h]) * C);
    sl[h] = l0[h] + l1[h]; sh[h] = h0[h] + h1[h];
  }
#pragma unroll
  for (int h = 0; h < 4; h++) { sl[h] += __shfl_xor_sync(0xffffffffu, sl[h], 1); sh[h] += __shfl_xor_sync(0xffffffffu, sh[h], 1); }
#pragma unroll
  for (int h = 0; h < 4; h++) { sl[h] += __shfl_xor_sync(0xffffffffu, sl[h], 2); sh[h] += __shfl_xor_sync(0xffffffffu, sh[h], 2); }
  uint32_t a0[4], a2[4], a3[4], b1[4];
#pragma unroll
  for (int h = 0; h < 4; h++) {
    const float il = __fdividef(1.f, sl[h]), ih = __fdividef(1.f, sh[h]);
    const float p0 = l0[h] * il, p1 = l1[h] * il, p2 = h0[h] * ih, p3 = h1[h] * ih;
    a0[h] = pack2(gt0 ? p0 : 0.f, gt1 ? p1 : 0.f);
    a2[h] = pack2(gt0 ? 0.f : p0, gt1 ? 0.f : p1);
    a3[h] = pack2(gt0 ? p2 : 0.f, gt1 ? p3 : 0.f);
    b1[h] = pack2(gt0 ? 0.f : p2, gt1 ? 0.f : p3);
  }
  float o0[4][4], o1[4][4];
#pragma unroll
  for (int h = 0; h < 4; h++) {
#pragma unroll
    for (int e = 0; e < 4; e++) { o0[h][e] = 0.f; o1[h][e] = 0.f; }
    mma16816(o0[h], a0[h], 0u, a2[h], a3[h], hv[4 * h + 2], vt[h][0]);
    mma16816(o1[h], a0[h], 0u, a2[h], a3[h], hv[4 * h + 3], vt[h][1]);
  }
#pragma unroll
  for (int h = 0; h < 4; h++) {
    mma1688(o0[h], 0u, b1[h], vt[h][2]);
    mma1688(o1[h], 0u, b1[h], vt[h][3]);
  }
#pragma unroll
  for (int h = 0; h < 4; h++) {
    o[h][0] = pack2(o0[h][0], o0[h][1]); o[h][1] = pack2(o0[h][2], o0[h][3]);
    o[h][2] = pack2(o1[h][0], o1[h][1]); o[h][3] = pack2(o1[h][2], o1[h][3]);
  }
}

__device__ __forceinline__ void stage_partial(const float (&a)[32], uint32_t stage_addr, uint32_t tag) {
#pragma unroll
  for (int i = 0; i < 4; i++) {
    uint32_t r0 = pack2(a[8 * i + 0], a[8 * i + 1]), r1 = pack2(a[8 * i + 2], a[8 * i + 3]);
    uint32_t r2 = pack2(a[8 * i + 4], a[8 * i + 5]), r3 = pack2(a[8 * i + 6], a[8 * i + 7]);
    r0 = (r0 & ~1u) | tag;
    r2 = (r2 & ~1u) | tag;
    asm volatile("st.shared.v4.b32 [%0], {%1,%2,%3,%4};" ::"r"(stage_addr + i * 2048), "r"(r0), "r"(r1), "r"(r2), "r"(r3) : "memory");
  }
}
__device__ __forceinline__ void bulk_store(void* dst, uint32_t src, uint32_t bytes) {
  asm volatile("cp.async.bulk.global.shared::cta.bulk_group [%0], [%1], %2;" ::"l"(dst), "r"(src), "r"(bytes) : "memory");
  asm volatile("cp.async.bulk.commit_group;" ::: "memory");
}
__device__ __forceinline__ void part_load(uint64_t (&a)[4], uint64_t (&b)[4], const ulonglong2* src) {
#pragma unroll
  for (int i = 0; i < 4; i++) ld_relaxed_v2(src + i * 128, a[i], b[i]);
}
__device__ __forceinline__ void part_check(uint64_t (&a)[4], uint64_t (&b)[4], const ulonglong2* src, uint32_t tag) {
  uint32_t n = 0;
  while (true) {
    bool ok = true;
#pragma unroll
    for (int i = 0; i < 4; i++) ok = ok && (((uint32_t)a[i] & 1u) == tag) && (((uint32_t)b[i] & 1u) == tag);
    if (ok || ++n >= SPIN_LIMIT) break;
    __nanosleep(100);
    part_load(a, b, src);
  }
}
__device__ __forceinline__ void part_add(float (&o)[32], const uint64_t (&a)[4], const uint64_t (&b)[4]) {
#pragma unroll
  for (int i = 0; i < 4; i++) {
    const uint32_t r0 = (uint32_t)a[i], r1 = (uint32_t)(a[i] >> 32), r2 = (uint32_t)b[i], r3 = (uint32_t)(b[i] >> 32);
    o[8 * i + 0] += bf_lo(r0); o[8 * i + 1] += bf_hi(r0);
    o[8 * i + 2] += bf_lo(r1); o[8 * i + 3] += bf_hi(r1);
    o[8 * i + 4] += bf_lo(r2); o[8 * i + 5] += bf_hi(r2);
    o[8 * i + 6] += bf_lo(r3); o[8 * i + 7] += bf_hi(r3);
  }
}

__device__ __forceinline__ void cs_publish(const uint4 (&v)[8], uint4* dst, int id, uint32_t tag) {
  float a[8];
#pragma unroll
  for (int e = 0; e < 8; e++) a[e] = 0.f;
#pragma unroll
  for (int r = 0; r < 8; r++) {
    a[0] += bf_lo(v[r].x); a[1] += bf_hi(v[r].x); a[2] += bf_lo(v[r].y); a[3] += bf_hi(v[r].y);
    a[4] += bf_lo(v[r].z); a[5] += bf_hi(v[r].z); a[6] += bf_lo(v[r].w); a[7] += bf_hi(v[r].w);
  }
#pragma unroll
  for (int e = 0; e < 8; e++) {
    a[e] += __shfl_xor_sync(0xffffffffu, a[e], 1);
    a[e] += __shfl_xor_sync(0xffffffffu, a[e], 2);
  }
  const int rg = id & 3;
  if (rg < 2) {
    const uint32_t x0 = (__float_as_uint(rg ? a[4] : a[0]) & ~1u) | tag, x1 = (__float_as_uint(rg ? a[5] : a[1]) & ~1u) | tag;
    const uint32_t x2 = (__float_as_uint(rg ? a[6] : a[2]) & ~1u) | tag, x3 = (__float_as_uint(rg ? a[7] : a[3]) & ~1u) | tag;
    asm volatile("st.relaxed.gpu.global.v4.b32 [%0], {%1,%2,%3,%4};" ::"l"(dst + 2 * (id >> 2) + rg), "r"(x0), "r"(x1), "r"(x2), "r"(x3) : "memory");
  }
}
__device__ __forceinline__ void cs_gather(const uint4* src, int id, uint32_t tag, uint32_t smem_dst, uint32_t bar) {
  const int k4 = id >> 1, hf = id & 1;
  const uint4* gp = src + hf * 8 * 48 + k4;
  uint4 v[8];
  uint32_t n = 0;
  bool ok;
  do {
    ok = true;
#pragma unroll
    for (int r = 0; r < 8; r++)
      asm volatile("ld.relaxed.gpu.global.v4.b32 {%0,%1,%2,%3}, [%4];" : "=r"(v[r].x), "=r"(v[r].y), "=r"(v[r].z), "=r"(v[r].w)
                   : "l"(gp + r * 48) : "memory");
#pragma unroll
    for (int r = 0; r < 8; r++) ok = ok && (((v[r].x & v[r].y & v[r].z & v[r].w & 1u) == tag) && (((v[r].x | v[r].y | v[r].z | v[r].w) & 1u) == tag));
  } while (!ok && ++n < SPIN_LIMIT);
  float s0 = 0.f, s1 = 0.f, s2 = 0.f, s3 = 0.f;
#pragma unroll
  for (int r = 0; r < 8; r++) {
    s0 += __uint_as_float(v[r].x); s1 += __uint_as_float(v[r].y); s2 += __uint_as_float(v[r].z); s3 += __uint_as_float(v[r].w);
  }
  s0 += __shfl_xor_sync(0xffffffffu, s0, 1); s1 += __shfl_xor_sync(0xffffffffu, s1, 1);
  s2 += __shfl_xor_sync(0xffffffffu, s2, 1); s3 += __shfl_xor_sync(0xffffffffu, s3, 1);
  if (hf == 0) {
    const uint32_t d0 = smem_dst + (2 * (k4 & 1)) * CS_STR + (k4 >> 1) * 8;
    asm volatile("st.shared.v2.f32 [%0], {%1,%2};" ::"r"(d0), "f"(s0), "f"(s1) : "memory");
    asm volatile("st.shared.v2.f32 [%0], {%1,%2};" ::"r"(d0 + CS_STR), "f"(s2), "f"(s3) : "memory");
  }
  __syncwarp();
  if ((id & 31) == 0) mbar_arrive(bar);
}

__device__ __forceinline__ void p2_unit(float (&acc)[32], const uint32_t (&af)[15][4], uint32_t bslot, bool first) {
  const uint64_t db = desc_b(bslot);
#pragma unroll
  for (int ks = 0; ks < 15; ks++) {
    if (first && ks == 0) wgmma_n64_rs_init(acc, af[0], db);
    else wgmma_n64_rs(acc, af[ks], db + (uint64_t)((ks * 2048) >> 4), 1);
  }
}

__global__ void __cluster_dims__(2, 1, 1) __launch_bounds__(NTHREADS, 1)
fused_kernel(const __grid_constant__ CUtensorMap mapX,
             const __grid_constant__ CUtensorMap mapWqkv, const __grid_constant__ CUtensorMap mapW1,
             const __grid_constant__ CUtensorMap mapWo, const __grid_constant__ CUtensorMap mapW2,
             const __nv_bfloat16* __restrict__ Wqkv, const __nv_bfloat16* __restrict__ W1,
             __nv_bfloat16* __restrict__ Out, Scratch* __restrict__ scr) {
  extern __shared__ uint8_t smem_raw[];
  const uint32_t sb = (smem_u32(smem_raw) + 1023u) & ~1023u;
  const int warp = threadIdx.x >> 5;
  const int cta = blockIdx.x;
  const int m = cta >> 3, c = cta & 7, j = c >> 1, p = c & 1;

  auto issue = [&](int i) {
    if (i < 16) {
      const uint32_t fb = sb + B_FULLA + 8 * (i & 3);
      const uint32_t dst = sb + RING_OFF + ((i + 2) & 3) * S_SLOT;
      mbar_expect_tx(fb, 24576);
      if (i < 8) {
#pragma unroll
        for (int s = 0; s < 3; s++) tma2d(dst + s * 8192, &mapWqkv, fb, s * 512 + 64 * c, 64 * i);
      } else {
#pragma unroll
        for (int s = 0; s < 3; s++) tma2d(dst + s * 8192, &mapW1, fb, 176 * c + 64 * s, 64 * (i - 8));
      }
    } else if (i < 24) {
      const int u = i - 16;
      const uint32_t fb = sb + B_FULLB + 8 * (u % 3);
      const uint32_t dst = sb + RING_OFF + ((u + 2) % 3) * U_SLOT;
      const int cs = (u < 3 || u == 7) ? c : (c ^ 1);
      const int blk = (u < 6) ? ((j + 1 + (u % 3)) & 3) : j;
      const int col = 256 * p + 64 * blk;
      mbar_expect_tx(fb, 30720);
      tma2d(dst, &mapWo, fb, col, 64 * cs);
      tma2d(dst + 8192, &mapW2, fb, col, 176 * cs);
    } else {
      const uint32_t fb = sb + B_FULLB + 8 * (8 % 3);
      const uint32_t dst = sb + RING_OFF + 1 * U_SLOT;
      mbar_expect_tx(fb, 16384);
      tma3d(dst, &mapX, fb, 256 * p + 64 * j, 0, 64 * m);
      tma3d(dst + 8192, &mapX, fb, 256 * p + 64 * j, 1, 64 * m);
    }
  };

  if (warp == 8) {
    if (elect_one()) {
      prefetch_tmap(&mapWqkv);
#pragma unroll
      for (int i = 0; i < 4; i++) mbar_init(sb + B_FULLA + 8 * i, 1);
      asm volatile("fence.mbarrier_init.release.cluster;" ::: "memory");
      issue(0); issue(1);
      TS(3);
    }
    __syncwarp();
  } else if (warp == 9) {
    if (elect_one()) {
      prefetch_tmap(&mapX);
      mbar_init(sb + B_XFULL, 1); mbar_init(sb + B_XFULL + 32, 1);
      asm volatile("fence.mbarrier_init.release.cluster;" ::: "memory");
      mbar_expect_tx(sb + B_XFULL, 16384); mbar_expect_tx(sb + B_XFULL + 32, 16384);
      tma3d(sb + XN_OFF, &mapX, sb + B_XFULL, 0, 0, 64 * m);
      tma3d(sb + XN_OFF + 65536, &mapX, sb + B_XFULL + 32, 0, 1, 64 * m);
      tma3d(sb + XN_OFF + 8192, &mapX, sb + B_XFULL, 64, 0, 64 * m);
      tma3d(sb + XN_OFF + 65536 + 8192, &mapX, sb + B_XFULL + 32, 64, 1, 64 * m);
    }
    __syncwarp();
  } else if (warp == 10) {
    if (elect_one()) {
#pragma unroll
      for (int i = 1; i < 4; i++) { mbar_init(sb + B_XFULL + 8 * i, 1); mbar_init(sb + B_XFULL + 32 + 8 * i, 1); }
      asm volatile("fence.mbarrier_init.release.cluster;" ::: "memory");
#pragma unroll
      for (int i = 1; i < 4; i++) { mbar_expect_tx(sb + B_XFULL + 8 * i, 16384); mbar_expect_tx(sb + B_XFULL + 32 + 8 * i, 16384); }
    }
    __syncwarp();
  } else if (warp == 11) {
    if (elect_one()) {
#pragma unroll
      for (int i = 0; i < 2; i++) {
        mbar_init(sb + B_FREE + 8 * i, 4); mbar_init(sb + B_RDYH + 8 * i, 1); mbar_init(sb + B_RDYO + 8 * i, 1); mbar_init(sb + B_A2FULL + 8 * i, 1);
      }
      asm volatile("fence.mbarrier_init.release.cluster;" ::: "memory");
      mbar_expect_tx(sb + B_A2FULL, 32768); mbar_expect_tx(sb + B_A2FULL + 8, 32768);
    }
    __syncwarp();
  } else if (warp == 0) {
    if (elect_one()) {
#pragma unroll
      for (int i = 0; i < 4; i++) mbar_init(sb + B_EMPTYA + 8 * i, 8);
#pragma unroll
      for (int i = 0; i < 3; i++) { mbar_init(sb + B_FULLB + 8 * i, 1); mbar_init(sb + B_EMPTYB + 8 * i, 8); }
      asm volatile("fence.mbarrier_init.release.cluster;" ::: "memory");
    }
    __syncwarp();
  } else if (warp == 1) {
    if (elect_one()) {
      mbar_init(sb + B_PEERDN, 2); mbar_init(sb + B_CSQ, 3); mbar_init(sb + B_CSF, 3);
      mbar_init(sb + B_XDEAD, 4); mbar_init(sb + B_XDEAD + 8, 4); mbar_init(sb + B_HALO, 1); mbar_init(sb + B_HALO + 8, 1);
#pragma unroll
      for (int i = 0; i < 6; i++) mbar_init(sb + B_SND + 8 * i, 4);
      asm volatile("fence.mbarrier_init.release.cluster;" ::: "memory");
    }
    __syncwarp();
  }
  __syncthreads();
  asm volatile("barrier.cluster.arrive.relaxed.aligned;" ::: "memory");

  if (warp >= 8) {
    asm volatile("setmaxnreg.dec.sync.aligned.u32 56;");
    if (warp == 8) {
      if (elect_one()) { issue(2); issue(3); }
      __syncwarp();
      asm volatile("barrier.cluster.wait.acquire.aligned;" ::: "memory");
      if (elect_one()) {
        prefetch_tmap(&mapW1); prefetch_tmap(&mapWo); prefetch_tmap(&mapW2);
        TS(0);
        for (int i = 4; i < 25; i++) {
          const int dep = (i < 16) ? i - 4 : (i == 16) ? 13 : (i < 19) ? 15 : i - 3;
          if (dep < 16) mbar_wait(sb + B_EMPTYA + 8 * (dep & 3), (dep >> 2) & 1);
          else mbar_wait(sb + B_EMPTYB + 8 * ((dep - 16) % 3), ((dep - 16) / 3) & 1);
          if (i == 4 || i == 6) {
            const int q = i >> 1, kc = 2 * q + p;
            tma3d_mc(sb + XN_OFF + kc * 8192, &mapX, sb + B_XFULL + 8 * q, 64 * kc, 0, 64 * m, (uint16_t)3);
            tma3d_mc(sb + XN_OFF + 65536 + kc * 8192, &mapX, sb + B_XFULL + 32 + 8 * q, 64 * kc, 1, 64 * m, (uint16_t)3);
          }
          issue(i);
        }
        TS(1);
      }
      __syncwarp();
    } else {
      const int lane = threadIdx.x & 31;
      if (warp == 9) {
        asm volatile("barrier.cluster.wait.acquire.aligned;" ::: "memory");
        if (elect_one()) {
          const int kc = 2 + p;
          tma3d_mc(sb + XN_OFF + kc * 8192, &mapX, sb + B_XFULL + 8, 64 * kc, 0, 64 * m, (uint16_t)3);
          tma3d_mc(sb + XN_OFF + 65536 + kc * 8192, &mapX, sb + B_XFULL + 32 + 8, 64 * kc, 1, 64 * m, (uint16_t)3);
        }
        __syncwarp();
      }
      uint4 pre[8];
      {
        const int id = (warp - 9) * 32 + lane, q = id >> 2, rg = id & 3;
        const __nv_bfloat16* wp = Wqkv + (size_t)(32 * m + 8 * rg) * 1536 + ((q >> 3) * 512 + 64 * c + 8 * (q & 7));
#pragma unroll
        for (int r = 0; r < 8; r++) pre[r] = ldg_nc(reinterpret_cast<const uint4*>(wp + r * 1536));
      }
      {
        const uint32_t epoch_h = scr->epoch[cta] + 1u, tag = epoch_h & 1u;
        if (lane == 0) asm volatile("st.shared.u32 [%0], %1;" ::"r"(sb + EPO_OFF), "r"(epoch_h) : "memory");
        const int id = (warp - 9) * 32 + lane;
        cs_publish(pre, scr->cs + (c * 2) * 16 * 48 + m * 48, id, tag);
        if (warp == 10) TSH(8);
        {
          const int q = id >> 2, rg = id & 3;
          const int col = 176 * c + 8 * q;
          const bool act = q < 22 && col < DFF;
          const __nv_bfloat16* wp = W1 + (act ? col : 0) + (size_t)(32 * m + 8 * rg) * DFF;
          uint4 v[8];
#pragma unroll
          for (int r = 0; r < 8; r++) v[r] = ldg_nc(reinterpret_cast<const uint4*>(wp + (size_t)r * DFF));
          if (!act) {
#pragma unroll
            for (int r = 0; r < 8; r++) v[r] = make_uint4(0, 0, 0, 0);
          }
          cs_publish(v, scr->cs + (c * 2 + 1) * 16 * 48 + m * 48, id, tag);
        }
        if (warp == 10) TSH(12);
        if (warp >= 10) {
          const int wq = warp - 10, row = 8 * c + (lane >> 2), qq = lane & 3;
#pragma unroll
          for (int q4 = 0; q4 < 4; q4++) mbar_wait(sb + B_XFULL + wq * 32 + 8 * q4, 0);
          const uint32_t xa = fresh_u32(sb) + XN_OFF + wq * 65536 + row * 128;
          float s0 = 0.f, s1 = 0.f, q0 = 0.f, q1 = 0.f;
#pragma unroll 1
          for (int kc = 0; kc < 8; kc += 4) {
            uint4 v[8];
#pragma unroll
            for (int e = 0; e < 8; e++) v[e] = lds128_nv(xa + (kc + (e >> 1)) * 8192 + (((2 * qq + (e & 1)) ^ (row & 7)) << 4));
#pragma unroll
            for (int e = 0; e < 8; e++) {
              float f;
              f = bf_lo(v[e].x); s0 += f; q0 = fmaf(f, f, q0);  f = bf_hi(v[e].x); s1 += f; q1 = fmaf(f, f, q1);
              f = bf_lo(v[e].y); s0 += f; q0 = fmaf(f, f, q0);  f = bf_hi(v[e].y); s1 += f; q1 = fmaf(f, f, q1);
              f = bf_lo(v[e].z); s0 += f; q0 = fmaf(f, f, q0);  f = bf_hi(v[e].z); s1 += f; q1 = fmaf(f, f, q1);
              f = bf_lo(v[e].w); s0 += f; q0 = fmaf(f, f, q0);  f = bf_hi(v[e].w); s1 += f; q1 = fmaf(f, f, q1);
            }
          }
          float sum = s0 + s1, sq = q0 + q1;
          sum += __shfl_xor_sync(0xffffffffu, sum, 1); sq += __shfl_xor_sync(0xffffffffu, sq, 1);
          sum += __shfl_xor_sync(0xffffffffu, sum, 2); sq += __shfl_xor_sync(0xffffffffu, sq, 2);
          const float mu = sum * (1.f / 512.f);
          const float r = rsqrtf(fmaxf(sq * (1.f / 512.f) - mu * mu, 0.f) + 1e-5f);
          if (qq == 0)
            asm volatile("st.relaxed.gpu.global.v2.b32 [%0], {%1,%2};" ::"l"(scr->stats + 128 * m + 2 * row + wq), "r"((__float_as_uint(r) & ~1u) | tag),
                         "r"((__float_as_uint(-mu * r) & ~1u) | tag) : "memory");
          if (warp == 10) TSH(9);
        }
        cs_gather(scr->cs + (c * 2) * 16 * 48, id, tag, sb + CSQ_OFF, sb + B_CSQ);
        if (warp == 10) TSH(10);
        cs_gather(scr->cs + (c * 2 + 1) * 16 * 48, id, tag, sb + CSF_OFF, sb + B_CSF);
        if (warp == 10) TSH(14);
      }
      if (warp == 9 && lane == 0) {
        TS(4);
        const int u2 = m >> 1;
        const int cs = (u2 < 3 || u2 == 7) ? c : (c ^ 1);
        const int blk = (u2 < 6) ? ((j + 1 + (u2 % 3)) & 3) : j;
        const int col = 256 * p + 64 * blk;
        if (m & 1) tma2d_prefetch(&mapW2, col, 176 * cs);
        else tma2d_prefetch(&mapWo, col, 64 * cs);
      }
      if (warp >= 10) {
        asm volatile("barrier.cluster.wait.acquire.aligned;" ::: "memory");
        const int w = warp - 10;
        const uint32_t src = sb + XN_OFF + w * 65536 + p * 32768 + lane * 16;
        if (m > 0) {
          const uint32_t epoch = scr->epoch[cta] + 1u;
          const ulonglong2* hp = scr->halo + ((cta - 8) * 2 + w) * 256 + lane;
          uint64_t ha[8], hb[8];
          uint32_t n = 0;
          bool ok;
          mbar_wait(sb + B_XDEAD + 8 * w, 0);
          do {
            ok = true;
#pragma unroll
            for (int i2 = 0; i2 < 8; i2++) ld_relaxed_v2(hp + i2 * 32, ha[i2], hb[i2]);
#pragma unroll
            for (int i2 = 0; i2 < 8; i2++) ok = ok && ((uint32_t)(ha[i2] >> 32) == epoch) && ((uint32_t)(hb[i2] >> 32) == epoch);
          } while (!__all_sync(0xffffffffu, ok) && ++n < SPIN_LIMIT);
#pragma unroll
          for (int hh = 0; hh < 4; hh++)
            asm volatile("st.shared.v4.b32 [%0], {%1,%2,%3,%4};" ::"r"(src + 3 * 2048 + hh * 512), "r"((uint32_t)ha[2 * hh]), "r"((uint32_t)hb[2 * hh]),
                         "r"((uint32_t)ha[2 * hh + 1]), "r"((uint32_t)hb[2 * hh + 1]) : "memory");
          __syncwarp();
          if (lane == 0) mbar_arrive(sb + B_HALO + 8 * w);
          TSH(16 + w);
        }
        if (elect_one()) {
          const uint32_t s0 = sb + XN_OFF + w * 65536 + p * 32768;
          const uint32_t d0 = mapa(s0, p ^ 1), rbar = mapa(sb + B_A2FULL + 8 * w, p ^ 1);
          mbar_wait(sb + B_RDYH + 8 * w, 0);
          mbar_wait_cluster(sb + B_FREE + 8 * w, 0);
          bulk_s2s(d0 + 8192, s0 + 8192, 24576, rbar);
        }
        __syncwarp();
        {
          const uint32_t d0 = mapa(src, p ^ 1), rbar = mapa(sb + B_A2FULL + 8 * w, p ^ 1);
          mbar_wait(sb + B_RDYO + 8 * w, 0);
#pragma unroll 1
          for (int it = 0; it < 16; it += 8) {
            uint4 v[8];
#pragma unroll
            for (int e = 0; e < 8; e++) v[e] = lds128(src + (it + e) * 512);
#pragma unroll
            for (int e = 0; e < 8; e++) st_async_v4(d0 + (it + e) * 512, v[e], rbar);
          }
        }
        if (elect_one()) {
#pragma unroll 1
          for (int r = 0; r < 3; r++) {
            mbar_wait(sb + B_SND + 8 * (w * 3 + r), 0);
            bulk_store(scr->part + ((((m * 8 + ((((j + 1 + r) & 3) << 1) | p)) * 3 + r) * 2 + w) * 4) * 128,
                       sb + XN_OFF + w * 65536 + (p ^ 1) * 32768 + r * 8192, 8192);
          }
          asm volatile("cp.async.bulk.wait_group.read 0;" ::: "memory");
        }
        __syncwarp();
        mbar_wait_cluster(sb + B_PEERDN, 0);
      }
    }
  } else {
    asm volatile("setmaxnreg.inc.sync.aligned.u32 224;");
    TS(16);
    asm volatile("barrier.cluster.wait.acquire.aligned;" ::: "memory");
    TS(17);
    uint32_t epoch_v = 0;
#define EPOCH epoch_v
#define PHASE_VARS                                                                                   \
    const uint32_t tix = fresh_tid(), ctx = fresh_cta(), sb = fresh_u32(sb0);                          \
    const int lane = tix & 31, w = tix >> 7, ww = (tix >> 5) & 3, tid = tix & 127;                    \
    const int cta = ctx, m = ctx >> 3, j = (ctx >> 1) & 3, p = ctx & 1, c = ctx & 7;                  \
    const int g = lane >> 2, qd = lane & 3;                                                           \
    const uint32_t xb = sb + XN_OFF + w * 65536;                                                      \
    const uint32_t lofs = (16 * ww + (lane & 7) + 8 * ((lane >> 3) & 1)) * 128;                       \
    const uint32_t lx = (uint32_t)(lane & 7), lu = (uint32_t)(lane >> 4);                             \
    (void)cta; (void)m; (void)j; (void)p; (void)c; (void)g; (void)qd; (void)xb; (void)lofs; (void)lx; (void)lu; (void)tid; (void)w; (void)ww;
#define TILE_ADDR(base, s) ((base) + lofs + ((((2u * (s)) + lu) ^ lx) << 4))
    const uint32_t sb0 = sb;

    float accQ[96];
#pragma unroll
    for (int i = 0; i < 96; i++) accQ[i] = 0.f;
    {
      PHASE_VARS
      uint64_t da = desc_a(xb);
#pragma unroll 1
      for (int kc = 0; kc < 8; kc++) {
        if ((kc & 1) == 0) mbar_wait(sb + B_XFULL + w * 32 + 4 * kc, 0);
        mbar_wait(sb + B_FULLA + 8 * (kc & 3), kc >> 2);
        TS(20 + kc);
        const uint64_t db = desc_b(sb + RING_OFF + ((kc + 2) & 3) * S_SLOT);
        wg_fence();
#pragma unroll
        for (int s = 0; s < 4; s++) wgmma_n192(accQ, da + s * 2, db + s * 128, (kc | s) ? 1 : 0);
        wg_commit();
        da += 512;
        if (kc > 0) {
          wg_wait<1>();
          if (lane == 0) mbar_arrive(sb + B_EMPTYA + 8 * ((kc - 1) & 3));
        }
      }
    }
    TS(4);
    float accF[88];
    float a_lo, b_lo, a_hi, b_hi;
    {
      uint32_t x0 = 0, x1 = 0, y0 = 0, y1 = 0;
#pragma unroll
      for (int kc = 0; kc < 8; kc++) {
        PHASE_VARS
        const int i = 8 + kc;
        mbar_wait(sb + B_FULLA + 8 * (i & 3), (i >> 2) & 1);
        TS(36 + kc);
        const uint64_t da = desc_a(xb) + (uint64_t)(kc * 512);
        const uint64_t db = desc_b(sb + RING_OFF + ((i + 2) & 3) * S_SLOT);
        wg_fence();
#pragma unroll
        for (int s = 0; s < 4; s++) {
          if (kc == 0 && s == 0) wgmma_n176_init(accF, da, db);
          else wgmma_n176(accF, da + s * 2, db + s * 128, 1);
        }
        wg_commit();
        wg_wait<1>();
        if (lane == 0) mbar_arrive(sb + B_EMPTYA + 8 * ((i - 1) & 3));
        if (kc == 1 || kc == 5) {
          if (lane == 0 && p == (kc >> 2)) mbar_arrive(sb + B_XDEAD + 8 * w);
        }
        if (kc == 4) {
          const uint2* sp = scr->stats + 128 * m + 2 * (16 * ww + g) + w;
          asm volatile("ld.relaxed.gpu.global.v2.b32 {%0,%1}, [%2];" : "=r"(x0), "=r"(x1) : "l"(sp) : "memory");
          asm volatile("ld.relaxed.gpu.global.v2.b32 {%0,%1}, [%2];" : "=r"(y0), "=r"(y1) : "l"(sp + 16) : "memory");
        }
        if (kc == 6) {
          mbar_wait(sb + B_CSQ, 0);
          asm volatile("ld.shared.u32 %0, [%1];" : "=r"(epoch_v) : "r"(sb + EPO_OFF) : "memory");
          const uint32_t tg = EPOCH & 1u;
          const uint2* sp = scr->stats + 128 * m + 2 * (16 * ww + g) + w;
          uint32_t n = 0;
          while (!(((x0 & x1 & y0 & y1 & 1u) == tg) && (((x0 | x1 | y0 | y1) & 1u) == tg)) && ++n < SPIN_LIMIT) {
            asm volatile("ld.relaxed.gpu.global.v2.b32 {%0,%1}, [%2];" : "=r"(x0), "=r"(x1) : "l"(sp) : "memory");
            asm volatile("ld.relaxed.gpu.global.v2.b32 {%0,%1}, [%2];" : "=r"(y0), "=r"(y1) : "l"(sp + 16) : "memory");
          }
          a_lo = __uint_as_float(x0); b_lo = __uint_as_float(x1); a_hi = __uint_as_float(y0); b_hi = __uint_as_float(y1);
          if (ww == 3 && m < 15) {
            reg_fence(accQ);
            const uint32_t csa = fresh_u32(sb) + CSQ_OFF + CS_STR * qd;
            ulonglong2* hp = scr->halo + (cta * 2 + w) * 256 + lane;
            const uint32_t epoch = EPOCH;
#pragma unroll
            for (int hh = 0; hh < 4; hh++) {
              const int gk = 8 + 2 * hh, gv = 16 + 2 * hh;
              const float4 ck = lds128f(csa + 8 * gk), cv = lds128f(csa + 8 * gv);
              const float2 c0 = make_float2(ck.x, ck.y), c1 = make_float2(ck.z, ck.w), c2 = make_float2(cv.x, cv.y), c3 = make_float2(cv.z, cv.w);
              const uint32_t k0 = pack2(fmaf(c0.x, b_hi, accQ[4 * gk + 2] * a_hi), fmaf(c0.y, b_hi, accQ[4 * gk + 3] * a_hi));
              const uint32_t k1 = pack2(fmaf(c1.x, b_hi, accQ[4 * gk + 6] * a_hi), fmaf(c1.y, b_hi, accQ[4 * gk + 7] * a_hi));
              const uint32_t v0 = movm(pack2(fmaf(c2.x, b_hi, accQ[4 * gv + 2] * a_hi), fmaf(c2.y, b_hi, accQ[4 * gv + 3] * a_hi)));
              const uint32_t v1 = movm(pack2(fmaf(c3.x, b_hi, accQ[4 * gv + 6] * a_hi), fmaf(c3.y, b_hi, accQ[4 * gv + 7] * a_hi)));
              st_relaxed_v2(hp + (2 * hh) * 32, mk64(k0, epoch), mk64(k1, epoch));
              st_relaxed_v2(hp + (2 * hh + 1) * 32, mk64(v0, epoch), mk64(v1, epoch));
            }
          }
        }
      }
    }
    uint32_t af[15][4];
    uint32_t qf[4][4], kf[4][4], vt[4][4], hvv[16];
    {
      PHASE_VARS
      mbar_wait(sb + B_CSF, 0);
      wg_wait<0>();
      reg_fence(accF);
      reg_fence(accQ);
      TS(7);
      if (lane == 0) {
        mbar_arrive(sb + B_EMPTYA + 8 * (15 & 3));
        mbar_arrive_remote(mapa(sb + B_FREE + 8 * w, p ^ 1));
      }
      const uint32_t csf = fresh_u32(sb) + CSF_OFF + CS_STR * qd, csq = csf - (CSF_OFF - CSQ_OFF);
      float4 ch[3], cq[3];
      ch[0] = lds128f_v(csf); cq[0] = lds128f_v(csq); ch[1] = lds128f_v(csf + 16); cq[1] = lds128f_v(csq + 16);
      wg_bar(1 + w);
      TS(18);
      const uint32_t ab = xb + p * 32768;
#pragma unroll
      for (int i = 0; i < 12; i++) {
        if (i + 2 < 11) ch[(i + 2) % 3] = lds128f_v(csf + 16 * (i + 2));
        if (i + 2 < 12) cq[(i + 2) % 3] = lds128f_v(csq + 16 * (i + 2));
        if (i < 11) {
          const float4 cc = ch[i % 3];
          const uint32_t r0 = pack2_relu(fmaf(cc.x, b_lo, accF[8 * i + 0] * a_lo), fmaf(cc.y, b_lo, accF[8 * i + 1] * a_lo));
          const uint32_t r1 = pack2_relu(fmaf(cc.x, b_hi, accF[8 * i + 2] * a_hi), fmaf(cc.y, b_hi, accF[8 * i + 3] * a_hi));
          const uint32_t r2 = pack2_relu(fmaf(cc.z, b_lo, accF[8 * i + 4] * a_lo), fmaf(cc.w, b_lo, accF[8 * i + 5] * a_lo));
          const uint32_t r3 = pack2_relu(fmaf(cc.z, b_hi, accF[8 * i + 6] * a_hi), fmaf(cc.w, b_hi, accF[8 * i + 7] * a_hi));
          stsm4(TILE_ADDR(ab + (1 + (i >> 2)) * 8192, i & 3), r0, r1, r2, r3);
        }
        {
          const float4 cs = cq[i % 3];
          const int hh = i & 3;
          const uint32_t lo_a = pack2(fmaf(cs.x, b_lo, accQ[8 * i + 0] * a_lo), fmaf(cs.y, b_lo, accQ[8 * i + 1] * a_lo));
          const uint32_t hi_a = pack2(fmaf(cs.x, b_hi, accQ[8 * i + 2] * a_hi), fmaf(cs.y, b_hi, accQ[8 * i + 3] * a_hi));
          const uint32_t lo_b = pack2(fmaf(cs.z, b_lo, accQ[8 * i + 4] * a_lo), fmaf(cs.w, b_lo, accQ[8 * i + 5] * a_lo));
          const uint32_t hi_b = pack2(fmaf(cs.z, b_hi, accQ[8 * i + 6] * a_hi), fmaf(cs.w, b_hi, accQ[8 * i + 7] * a_hi));
          if (i < 4) { qf[hh][0] = lo_a; qf[hh][1] = hi_a; qf[hh][2] = lo_b; qf[hh][3] = hi_b; }
          else if (i < 8) { kf[hh][0] = lo_a; kf[hh][1] = lo_b; kf[hh][2] = hi_a; kf[hh][3] = hi_b; }
          else { vt[hh][0] = movm(lo_a); vt[hh][1] = movm(lo_b); vt[hh][2] = movm(hi_a); vt[hh][3] = movm(hi_b); }
        }
      }
      TS(8);
      const uint32_t hb0 = ab + lane * 16;
      if (ww < 3) {
#pragma unroll
        for (int hh = 0; hh < 4; hh++)
          asm volatile("st.shared.v4.b32 [%0], {%1,%2,%3,%4};" ::"r"(hb0 + ww * 2048 + hh * 512), "r"(kf[hh][2]), "r"(kf[hh][3]), "r"(vt[hh][2]), "r"(vt[hh][3]) : "memory");
      }
      if (m > 0) mbar_wait(sb + B_HALO + 8 * w, 0);
      TS(19);
      fence_async_smem();
      wg_bar(1 + w);
      if (tid == 0) mbar_arrive(sb + B_RDYH + 8 * w);
      const uint32_t ha = hb0 + ((ww + 3) & 3) * 2048;
#pragma unroll
      for (int hh = 0; hh < 4; hh++)
        asm volatile("ld.shared.v4.b32 {%0,%1,%2,%3}, [%4];" : "=r"(hvv[4 * hh]), "=r"(hvv[4 * hh + 1]), "=r"(hvv[4 * hh + 2]), "=r"(hvv[4 * hh + 3]) : "r"(ha + hh * 512) : "memory");
      if (m == 0 && ww == 0) {
#pragma unroll
        for (int i2 = 0; i2 < 16; i2++) hvv[i2] = 0u;
      }
    }
    TS(5);
    {
      PHASE_VARS
      const bool gt0 = (2 * qd) > g, gt1 = (2 * qd + 1) > g;
      const bool halo_valid = !(m == 0 && ww == 0);
      const uint32_t ab = xb + p * 32768;
#pragma unroll
      for (int ks = 4; ks < 15; ks++) ldsm4(af[ks], TILE_ADDR(ab + (ks >> 2) * 8192, ks & 3));
      uint32_t of[4][4];
      attn4(qf, kf, vt, hvv, halo_valid, gt0, gt1, of);
      wg_bar(1 + w);
#pragma unroll
      for (int hh = 0; hh < 4; hh++) {
        stsm4(TILE_ADDR(ab, hh), of[hh][0], of[hh][1], of[hh][2], of[hh][3]);
#pragma unroll
        for (int e = 0; e < 4; e++) af[hh][e] = of[hh][e];
      }
      asm volatile("bar.sync 4, 256;" ::: "memory");
      if (tid == 0) mbar_arrive(sb + B_RDYO + 8 * w);
    }
    TS(6);

    const uint32_t tag = EPOCH & 1u;
    float R0[32], R1[32], R2[32], O[32];
#define P2_WAIT(u) do { TS(44 + (u)); mbar_wait(sb + B_FULLB + 8 * ((u) % 3), ((u) / 3) & 1); TS(52 + (u)); } while (0)
#define P2_SLOT(u) (sb + RING_OFF + (((u) + 2) % 3) * U_SLOT)
#define P2_REL(u) do { if (lane == 0) mbar_arrive(sb + B_EMPTYB + 8 * ((u) % 3)); } while (0)
#define P2_SEND(R, r) do { reg_fence(R); stage_partial(R, xb + (p ^ 1) * 32768 + (r) * 8192 + tid * 16, tag); fence_async_smem(); __syncwarp(); \
                           if (lane == 0) mbar_arrive(sb + B_SND + 8 * (w * 3 + (r))); } while (0)
#define LOAD_FRAGS(dst, base)                                                              \
    _Pragma("unroll") for (int ks = 0; ks < 15; ks++) ldsm4(dst[ks], TILE_ADDR((base) + (ks >> 2) * 8192, ks & 3));
#define TURN_WAIT() asm volatile("bar.sync %0, 256;" ::"r"(6 + w) : "memory")
#define TURN_PASS() asm volatile("bar.arrive %0, 256;" ::"r"(7 - w) : "memory")
#define P2_UNIT(u, ACC, FR, FIRST) do { P2_WAIT(u); TURN_WAIT(); wg_fence(); p2_unit(ACC, FR, P2_SLOT(u), FIRST); wg_commit(); \
                                        TURN_PASS(); wg_wait<0>(); P2_REL(u); } while (0)
    { PHASE_VARS if (w == 1) TURN_PASS(); }
    { PHASE_VARS P2_UNIT(0, R0, af, true); }
    { PHASE_VARS P2_UNIT(1, R1, af, true); }
    uint32_t pf[15][4];
    { PHASE_VARS P2_UNIT(2, R2, af, true);
      TS(9);
      mbar_wait(sb + B_A2FULL + 8 * w, 0);
      if (tid == 0) mbar_arrive_remote(mapa(sb + B_PEERDN, p ^ 1));
      TS(10);
      LOAD_FRAGS(pf, xb + (p ^ 1) * 32768) }
    { PHASE_VARS P2_UNIT(3, R0, pf, false); P2_SEND(R0, 0); }
    { PHASE_VARS P2_UNIT(4, R1, pf, false); P2_SEND(R1, 1); TS(33); }
    { PHASE_VARS P2_UNIT(5, R2, pf, false); TS(34); P2_SEND(R2, 2); TS(35); }
    uint64_t pa0[4], pb0[4], pa1[4], pb1[4], pa2[4], pb2[4];
#define P2_SRC(r) (scr->part + (((cta * 3 + (r)) * 2 + w) * 4) * 128 + tid)
    { PHASE_VARS P2_UNIT(6, O, pf, true);
      LOAD_FRAGS(af, xb + p * 32768)
      part_load(pa0, pb0, P2_SRC(0)); }
    TS(11);
    { PHASE_VARS
      P2_WAIT(7); TURN_WAIT(); wg_fence(); p2_unit(O, af, P2_SLOT(7), false); wg_commit();
      if (w == 0) TURN_PASS();
      TS(28);
      part_load(pa1, pb1, P2_SRC(1)); }
    {
      PHASE_VARS
      uint32_t rs[4][4];
      mbar_wait(sb + B_FULLB + 8 * (8 % 3), (8 / 3) & 1);
      const uint32_t rb = sb + RING_OFF + 1 * U_SLOT + w * 8192;
#pragma unroll
      for (int s = 0; s < 4; s++) ldsm4(rs[s], TILE_ADDR(rb, s));
      TS(30);
      wg_wait<0>();
      reg_fence(O);
      TS(13);
      part_load(pa2, pb2, P2_SRC(2));
#pragma unroll
      for (int s = 0; s < 4; s++) {
#pragma unroll
        for (int e = 0; e < 4; e++) { O[8 * s + 2 * e] += bf_lo(rs[s][e]); O[8 * s + 2 * e + 1] += bf_hi(rs[s][e]); }
      }
      part_check(pa0, pb0, P2_SRC(0), tag);
      TS(31);
      part_add(O, pa0, pb0);
      part_check(pa1, pb1, P2_SRC(1), tag);
      TS(32);
      part_add(O, pa1, pb1);
      part_check(pa2, pb2, P2_SRC(2), tag);
      part_add(O, pa2, pb2);
      TS(12);
      __syncwarp();
#pragma unroll
      for (int s = 0; s < 4; s++)
        stsm4(TILE_ADDR(rb, s), pack2(O[8 * s + 0], O[8 * s + 1]), pack2(O[8 * s + 2], O[8 * s + 3]),
              pack2(O[8 * s + 4], O[8 * s + 5]), pack2(O[8 * s + 6], O[8 * s + 7]));
      __syncwarp();
      {
        const int un = lane & 7;
#pragma unroll
        for (int i = 0; i < 4; i++) {
          const int r = 16 * ww + 4 * i + (lane >> 3);
          const uint4 v = lds128(rb + r * 128 + ((un ^ (r & 7)) << 4));
          __nv_bfloat16* op = Out + (size_t)(128 * m + 2 * r + w) * DM + 256 * p + 64 * j + 8 * un;
          asm volatile("st.global.v4.b32 [%0], {%1,%2,%3,%4};" ::"l"(op), "r"(v.x), "r"(v.y), "r"(v.z), "r"(v.w) : "memory");
        }
      }
      if (tix < 32) {
        asm volatile("bar.sync 3, 256;" ::: "memory");
        if (lane == 0) scr->epoch[cta] = EPOCH;
      } else {
        asm volatile("bar.arrive 3, 256;" ::: "memory");
      }
    }
    TS(14);
  }
}

typedef CUresult (*EncodeFn)(CUtensorMap*, CUtensorMapDataType, cuuint32_t, void*, const cuuint64_t*, const cuuint64_t*,
                             const cuuint32_t*, const cuuint32_t*, CUtensorMapInterleave, CUtensorMapSwizzle,
                             CUtensorMapL2promotion, CUtensorMapFloatOOBfill);

static void make_map2d(EncodeFn enc, CUtensorMap* mp, const void* ptr, uint64_t cols, uint64_t rows, uint32_t box_rows) {
  cuuint64_t gd[2] = {cols, rows};
  cuuint64_t gs[1] = {cols * 2};
  cuuint32_t bx[2] = {64, box_rows};
  cuuint32_t es[2] = {1, 1};
  enc(mp, CU_TENSOR_MAP_DATA_TYPE_BFLOAT16, 2, const_cast<void*>(ptr), gd, gs, bx, es, CU_TENSOR_MAP_INTERLEAVE_NONE,
      CU_TENSOR_MAP_SWIZZLE_128B, CU_TENSOR_MAP_L2_PROMOTION_L2_256B, CU_TENSOR_MAP_FLOAT_OOB_FILL_NONE);
}
static void make_map_tok(EncodeFn enc, CUtensorMap* mp, const void* ptr) {
  cuuint64_t gd[3] = {512, 2, 1024};
  cuuint64_t gs[2] = {1024, 2048};
  cuuint32_t bx[3] = {64, 1, 64};
  cuuint32_t es[3] = {1, 1, 1};
  enc(mp, CU_TENSOR_MAP_DATA_TYPE_BFLOAT16, 3, const_cast<void*>(ptr), gd, gs, bx, es, CU_TENSOR_MAP_INTERLEAVE_NONE,
      CU_TENSOR_MAP_SWIZZLE_128B, CU_TENSOR_MAP_L2_PROMOTION_L2_256B, CU_TENSOR_MAP_FLOAT_OOB_FILL_NONE);
}

}

extern "C" void kernel_launch(void* const* d_in, const int* in_sizes, int n_in, void* d_out, int out_size) {
  using namespace fused;
  (void)in_sizes; (void)n_in; (void)out_size;
  static EncodeFn enc = nullptr;
  static void* scratch = nullptr;
  if (!enc) {
    void* fn = nullptr;
    cudaDriverEntryPointQueryResult qr;
    cudaGetDriverEntryPoint("cuTensorMapEncodeTiled", &fn, cudaEnableDefault, &qr);
    enc = (EncodeFn)fn;
    cudaFuncSetAttribute(fused_kernel, cudaFuncAttributeMaxDynamicSharedMemorySize, SMEM_BYTES);
    cudaGetSymbolAddress(&scratch, g_scratch);
  }
  CUtensorMap mX, mWqkv, mW1, mWo, mW2;
  make_map_tok(enc, &mX, d_in[0]);
  make_map2d(enc, &mWqkv, d_in[1], 1536, 512, 64);
  make_map2d(enc, &mWo, d_in[2], 512, 512, 64);
  make_map2d(enc, &mW1, d_in[4], 1376, 512, 64);
  make_map2d(enc, &mW2, d_in[5], 512, 1376, 176);
  fused_kernel<<<NCTA, NTHREADS, SMEM_BYTES, cudaStreamPerThread>>>(mX, mWqkv, mW1, mWo, mW2,
      (const __nv_bfloat16*)d_in[1], (const __nv_bfloat16*)d_in[4], (__nv_bfloat16*)d_out, (Scratch*)scratch);
}
```
